```python
import torch

def _softmax(x, axis=-1):
    return torch.softmax(x, dim=axis)
def _gelu(x):
    return torch.nn.functional.gelu(x, approximate="tanh")
def _silu(x):
    return torch.nn.functional.silu(x)
def _sigmoid(x):
    return torch.sigmoid(x)
def _layernorm(x, axis=-1, eps=1e-5):
    m = x.mean(dim=axis, keepdim=True)
    v = x.var(dim=axis, keepdim=True, unbiased=False)
    return (x - m) / torch.sqrt(v + eps)
def _scatter_add(tgt, idx, src, axis=0):
    return tgt.clone().index_add_(axis, idx, src)
def _segment_sum(src, seg, n):
    out = torch.zeros((n,) + src.shape[1:], dtype=src.dtype)
    return out.index_add_(0, seg, src)
def _pad(x, pw):
    flat = tuple(v for pair in reversed(pw) for v in pair)
    return torch.nn.functional.pad(x, flat)

kernel_name = 'sequential_preLN__gqa_block_cached__dense_activation_gelu__decode'

def setup_inputs():

    _w = (lambda a: (lambda t: t.to(torch.bfloat16) if t.is_floating_point() else t)(torch.as_tensor(a)))
    def _A_setup():
        B, Sq, D = 2, 1, 512
        Hq, Hkv, Sk, Dh = 32, 8, 8192, 128
        assert Hq % Hkv == 0, (Hq, Hkv)
        return {
            "x": _w((lambda *s: torch.randn(*s, dtype=torch.bfloat16) * 0.05)(B, Sq, D)),
            "k_cache": _w((lambda *s: torch.randn(*s, dtype=torch.bfloat16) * 3.2)(B, Hkv, Sk, Dh)),
            "v_cache": _w((lambda *s: torch.randn(*s, dtype=torch.bfloat16) * 0.8)(B, Hkv, Sk, Dh)),
            "wq": _w((lambda *s: torch.randn(*s, dtype=torch.bfloat16) * 3.2)(D, Hq * Dh) * (D ** -0.5)),
            "wo": _w((lambda *s: torch.randn(*s, dtype=torch.bfloat16) * 0.8)(Hq * Dh, D) * ((Hq * Dh) ** -0.5)),
        }
    _A_in = _A_setup()

    def _B_setup():
        B, S, D, F = 2, 1, 512, 1792
        return {
            "x": _w((lambda *s: torch.randn(*s, dtype=torch.bfloat16) * 0.05)(B, S, D)),
            "w1": _w((lambda *s: torch.randn(*s, dtype=torch.bfloat16) * 3.2)(D, F) * (D ** -0.5)),
            "b1": _w((lambda *s: torch.randn(*s, dtype=torch.bfloat16) * 3.2)(F) * 0.01),
            "w2": _w((lambda *s: torch.randn(*s, dtype=torch.bfloat16) * 0.8)(F, D) * (F ** -0.5)),
            "b2": _w((lambda *s: torch.randn(*s, dtype=torch.bfloat16) * 0.8)(D) * 0.01),
        }
    _B_in = _B_setup()

    return {
        "A_x": _A_in["x"],
        "A_k_cache": _A_in["k_cache"],
        "A_v_cache": _A_in["v_cache"],
        "A_wq": _A_in["wq"],
        "A_wo": _A_in["wo"],
        "B_x": _B_in["x"],
        "B_w1": _B_in["w1"],
        "B_b1": _B_in["b1"],
        "B_w2": _B_in["w2"],
        "B_b2": _B_in["b2"],
    }

def reference(A_x, A_k_cache, A_v_cache, A_wq, A_wo, B_x, B_w1, B_b1, B_w2, B_b2):
    def _A_ref(x, k_cache, v_cache, wq, wo):
        B, Sq, D = x.shape
        Hq, Dh = 32, 128
        Hkv = k_cache.shape[1]
        rep = Hq // Hkv
        q = (lambda x, *d: x.permute(*d))((x @ wq).reshape(B, Sq, Hq, Dh), 0, 2, 1, 3)
        k = (lambda x, n, axis: torch.repeat_interleave(x, n, dim=axis))(k_cache, rep, axis=1)
        v = (lambda x, n, axis: torch.repeat_interleave(x, n, dim=axis))(v_cache, rep, axis=1)
        scores = torch.einsum("bhqd,bhkd->bhqk", q, k) * (Dh ** -0.5)
        p = _softmax(scores, axis=-1)
        o = torch.einsum("bhqk,bhkd->bhqd", p, v)
        return (lambda x, *d: x.permute(*d))(o, 0, 2, 1, 3).reshape(B, Sq, Hq * Dh) @ wo

    def _B_ref(x, w1, b1, w2, b2):
        h = torch.einsum("bsd,df->bsf", x, w1) + b1
        h = _gelu(h)
        return torch.einsum("bsf,fd->bsd", h, w2) + b2

    x = A_x
    h = x + _A_ref(_layernorm(x, axis=-1), A_k_cache, A_v_cache, A_wq, A_wo)
    h2 = h + _B_ref(_layernorm(h, axis=-1), B_w1, B_b1, B_w2, B_b2)
    return h2
```

```cpp
#include <cuda_runtime.h>
#include <cuda_bf16.h>
#include <cuda.h>
#include <stdint.h>

#define NSLOT 6
#define SLOTB 32768
#define NFILL 25
#define NFF 112
__device__ unsigned g_epoch = 1;
__device__ unsigned g_ml[128 * 8];
__device__ unsigned g_x1[32 * 512];
__device__ unsigned g_x2[1024 * NFF];

__device__ __forceinline__ uint32_t s32(const void* p) { return (uint32_t)__cvta_generic_to_shared(p); }
__device__ __forceinline__ void mb_init(uint32_t b, int c) { asm volatile("mbarrier.init.shared::cta.b64 [%0], %1;" ::"r"(b), "r"(c)); }
__device__ __forceinline__ void mb_wait(uint32_t b, uint32_t ph) {
    uint32_t ok = 0;
    for (int it = 0; it < (1 << 24) && !ok; it++)
        asm volatile("{.reg .pred p; mbarrier.try_wait.parity.shared::cta.b64 p, [%1], %2; selp.u32 %0,1,0,p;}" : "=r"(ok) : "r"(b), "r"(ph) : "memory");
}
__device__ __forceinline__ void mb_arrive(uint32_t b) { asm volatile("mbarrier.arrive.shared::cta.b64 _, [%0];" ::"r"(b) : "memory"); }
__device__ __forceinline__ void mb_expect(uint32_t b, uint32_t n) { asm volatile("mbarrier.arrive.expect_tx.shared::cta.b64 _, [%0], %1;" ::"r"(b), "r"(n) : "memory"); }
__device__ __forceinline__ void tma2d(uint32_t dst, const CUtensorMap* m, int c0, int c1, uint32_t b) {
    asm volatile("cp.async.bulk.tensor.2d.shared::cluster.global.mbarrier::complete_tx::bytes [%0], [%1, {%3, %4}], [%2];" ::"r"(dst), "l"(m), "r"(b), "r"(c0), "r"(c1) : "memory");
}
__device__ __forceinline__ void bulk1d(uint32_t dst, const void* src, uint32_t n, uint32_t b) {
    asm volatile("cp.async.bulk.shared::cluster.global.mbarrier::complete_tx::bytes [%0], [%1], %2, [%3];" ::"r"(dst), "l"(src), "r"(n), "r"(b) : "memory");
}
__device__ __forceinline__ void cl_sync() {
    asm volatile("barrier.cluster.arrive.release.aligned;\nbarrier.cluster.wait.acquire.aligned;" ::: "memory");
}
__device__ __forceinline__ void st_cl(uint32_t laddr, int rank, float v) {
    uint32_t ra;
    asm volatile("mapa.shared::cluster.u32 %0, %1, %2;" : "=r"(ra) : "r"(laddr), "r"(rank));
    asm volatile("st.shared::cluster.f32 [%0], %1;" ::"r"(ra), "f"(v) : "memory");
}
__device__ __forceinline__ void mma(float* c, uint32_t a0, uint32_t a2, uint32_t b0, uint32_t b1) {
    asm volatile("mma.sync.aligned.m16n8k16.row.col.f32.bf16.bf16.f32 {%0,%1,%2,%3}, {%4,%5,%6,%5}, {%7,%8}, {%0,%1,%2,%3};"
                 : "+f"(c[0]), "+f"(c[1]), "+f"(c[2]), "+f"(c[3]) : "r"(a0), "r"(0u), "r"(a2), "r"(b0), "r"(b1));
}
__device__ __forceinline__ unsigned tagw(float v, unsigned t) { return (__float_as_uint(v) & ~3u) | t; }
__device__ __forceinline__ void stg(unsigned* p, unsigned v) { asm volatile("st.relaxed.gpu.global.u32 [%0], %1;" ::"l"(p), "r"(v) : "memory"); }
__device__ __forceinline__ unsigned ldg1(const unsigned* p) { unsigned v; asm volatile("ld.relaxed.gpu.global.u32 %0, [%1];" : "=r"(v) : "l"(p) : "memory"); return v; }
__device__ __forceinline__ uint4 ldg4(const unsigned* p) { uint4 v; asm volatile("ld.relaxed.gpu.global.v4.u32 {%0,%1,%2,%3}, [%4];" : "=r"(v.x), "=r"(v.y), "=r"(v.z), "=r"(v.w) : "l"(p) : "memory"); return v; }
__device__ __forceinline__ float bfr(float v) { return __bfloat162float(__float2bfloat16(v)); }
__device__ __forceinline__ float2 bf2(uint32_t u) { return make_float2(__uint_as_float(u << 16), __uint_as_float(u & 0xffff0000u)); }
__device__ __forceinline__ uint32_t pk(float a, float b) { __nv_bfloat162 h = __floats2bfloat162_rn(a, b); return *(uint32_t*)&h; }

struct Sm {
    unsigned char slots[NSLOT * SLOTB];
    float obuf[8 * 512];
    float xn[1024];
    float h[1024];
    float recv[4 * 128];
    float red[8 * 32];
    __nv_bfloat16 q[512];
    float stat[64];
    float g[32];
    unsigned long long full[NSLOT], empty[NSLOT];
};

__device__ void layernorm(const float* src, float* dst, float* red, int tid) {
    float a = src[tid], b = src[tid + 256];
    float s = a + b;
    for (int o = 16; o; o >>= 1) s += __shfl_xor_sync(~0u, s, o);
    if ((tid & 31) == 0) red[tid >> 5] = s;
    asm volatile("bar.sync 1, 256;");
    s = 0; for (int i = 0; i < 8; i++) s += red[i];
    float m = s * (1.f / 512);
    float v = (a - m) * (a - m) + (b - m) * (b - m);
    for (int o = 16; o; o >>= 1) v += __shfl_xor_sync(~0u, v, o);
    if ((tid & 31) == 0) red[8 + (tid >> 5)] = v;
    asm volatile("bar.sync 1, 256;");
    v = 0; for (int i = 0; i < 8; i++) v += red[8 + i];
    float r = rsqrtf(v * (1.f / 512) + 1e-5f);
    dst[tid] = bfr((a - m) * r); dst[tid + 256] = bfr((b - m) * r);
    asm volatile("bar.sync 1, 256;");
}

__global__ void __launch_bounds__(288, 1) fused(const __grid_constant__ CUtensorMap mk, const __grid_constant__ CUtensorMap mv,
    const __grid_constant__ CUtensorMap mq, const __grid_constant__ CUtensorMap m1,
    const __nv_bfloat16* __restrict__ x, const __nv_bfloat16* __restrict__ wo, const __nv_bfloat16* __restrict__ b1,
    const __nv_bfloat16* __restrict__ w2, const __nv_bfloat16* __restrict__ b2, __nv_bfloat16* __restrict__ out) {
    extern __shared__ unsigned char raw[];
    Sm& S = *(Sm*)(((uintptr_t)raw + 1023) & ~(uintptr_t)1023);
    const int tid = threadIdx.x, warp = tid >> 5, lane = tid & 31;
    const int cta = blockIdx.x, r = cta & 3, grp = cta >> 3, b = grp >> 3, hkv = grp & 7;
    const uint32_t sl0 = s32(S.slots), fb = s32(S.full), eb = s32(S.empty);
    if (tid == 0) {
        for (int i = 0; i < NSLOT; i++) { mb_init(fb + 8 * i, 1); mb_init(eb + 8 * i, 8); }
        asm volatile("fence.mbarrier_init.release.cluster;" ::: "memory");
    }
    cl_sync();
    if (warp == 8) {
        for (int f = 0; f < NFILL; f++) {
            if (f == 10) cl_sync();
            if (lane == 0) {
                int s = f % NSLOT; uint32_t d = sl0 + s * SLOTB, bar = fb + 8 * s;
                mb_wait(eb + 8 * s, ((f / NSLOT) & 1) ^ 1);
                if (f == 24 && cta >= NFF) continue;
                mb_expect(bar, SLOTB);
                if (f < 4) tma2d(d, &mq, hkv * 512 + r * 128 + (f >> 1) * 64, (f & 1) * 256, bar);
                else if (f < 20) {
                    const CUtensorMap* m = f < 12 ? &mk : &mv; int row = cta * 1024 + ((f - 4) & 7) * 128;
                    tma2d(d, m, 0, row, bar); tma2d(d + 16384, m, 64, row, bar);
                } else if (f < 24) bulk1d(d, wo + (size_t)(hkv * 512 + r * 128 + (f - 20) * 32) * 512, SLOTB, bar);
                else { tma2d(d, &m1, cta * 16, 0, bar); tma2d(d + 8192, &m1, cta * 16, 256, bar); bulk1d(d + 16384, w2 + (size_t)cta * 16 * 512, 16384, bar); }
            }
            __syncwarp();
        }
        cl_sync(); cl_sync(); cl_sync();
        return;
    }
    const unsigned tag = ldg1(&g_epoch) & 3;
    int f = 0;
#define WAITF() mb_wait(fb + 8 * (f % NSLOT), (f / NSLOT) & 1)
#define RELF() do { __syncwarp(); if (lane == 0) mb_arrive(eb + 8 * (f % NSLOT)); f++; } while (0)
    S.h[tid] = __bfloat162float(x[b * 512 + tid]); S.h[tid + 256] = __bfloat162float(x[b * 512 + 256 + tid]);
    asm volatile("bar.sync 1, 256;");
    layernorm(S.h, S.xn, S.red, tid);
    {
        for (int ch = 0; ch < 2; ch++) {
            float a0 = 0, a1 = 0;
            for (int rh = 0; rh < 2; rh++) {
                WAITF();
                const uint32_t* w = (const uint32_t*)(S.slots + (f % NSLOT) * SLOTB);
#pragma unroll 8
                for (int i = 0; i < 32; i++) { int row = warp * 32 + i; float2 wv = bf2(w[row * 32 + lane]); float xv = S.xn[rh * 256 + row]; a0 += xv * wv.x; a1 += xv * wv.y; }
                RELF();
            }
            S.obuf[warp * 128 + ch * 64 + lane * 2] = a0; S.obuf[warp * 128 + ch * 64 + lane * 2 + 1] = a1;
        }
        asm volatile("bar.sync 1, 256;");
        if (tid < 128) {
            float s = 0; for (int i = 0; i < 8; i++) s += S.obuf[i * 128 + tid];
            uint32_t la = s32(&S.q[r * 128 + tid]); unsigned short hv = __bfloat16_as_ushort(__float2bfloat16(s));
            for (int d = 0; d < 4; d++) { uint32_t ra; asm volatile("mapa.shared::cluster.u32 %0, %1, %2;" : "=r"(ra) : "r"(la), "r"(d)); asm volatile("st.shared::cluster.u16 [%0], %1;" ::"r"(ra), "h"(hv) : "memory"); }
        }
    }
    cl_sync();
    uint32_t qa[8][2];
    {
        int row = lane >> 2; const uint32_t* qw = (const uint32_t*)S.q;
#pragma unroll
        for (int k = 0; k < 8; k++) { qa[k][0] = row < 4 ? qw[row * 64 + k * 8 + (lane & 3)] : 0; qa[k][1] = row < 4 ? qw[row * 64 + k * 8 + 4 + (lane & 3)] : 0; }
    }
    float sc[8][4];
    const int mi = lane >> 3;
#pragma unroll
    for (int t = 0; t < 8; t++) {
        WAITF();
        float c0[4] = {0, 0, 0, 0}, c1[4] = {0, 0, 0, 0};
        int key = warp * 16 + (mi >> 1) * 8 + (lane & 7);
        uint32_t base = sl0 + (f % NSLOT) * SLOTB + key * 128;
#pragma unroll
        for (int k = 0; k < 8; k++) {
            uint32_t b0, b1_, b2_, b3; int ch = (k & 3) * 2 + (mi & 1);
            asm volatile("ldmatrix.sync.aligned.m8n8.x4.shared.b16 {%0,%1,%2,%3}, [%4];" : "=r"(b0), "=r"(b1_), "=r"(b2_), "=r"(b3) : "r"(base + (k >> 2) * 16384 + ((ch ^ (key & 7)) << 4)));
            mma(c0, qa[k][0], qa[k][1], b0, b1_); mma(c1, qa[k][0], qa[k][1], b2_, b3);
        }
        RELF();
        sc[t][0] = c0[0]; sc[t][1] = c0[1]; sc[t][2] = c1[0]; sc[t][3] = c1[1];
    }
    const float kS = 0.08838834764831845f * 1.4426950408889634f;
    float mx = -1e30f;
#pragma unroll
    for (int t = 0; t < 8; t++) for (int i = 0; i < 4; i++) mx = fmaxf(mx, sc[t][i] * kS);
    mx = fmaxf(mx, __shfl_xor_sync(~0u, mx, 1)); mx = fmaxf(mx, __shfl_xor_sync(~0u, mx, 2));
    if (lane < 16 && (lane & 3) == 0) S.red[warp * 4 + (lane >> 2)] = mx;
    asm volatile("bar.sync 1, 256;");
    { int row = (lane >> 2) & 3; mx = S.red[row]; for (int i = 1; i < 8; i++) mx = fmaxf(mx, S.red[i * 4 + row]); }
    uint32_t pa[8][2]; float l = 0;
#pragma unroll
    for (int t = 0; t < 8; t++) {
        float p[4]; for (int i = 0; i < 4; i++) { p[i] = bfr(exp2f(sc[t][i] * kS - mx)); l += p[i]; }
        pa[t][0] = pk(p[0], p[1]); pa[t][1] = pk(p[2], p[3]);
    }
    l += __shfl_xor_sync(~0u, l, 1); l += __shfl_xor_sync(~0u, l, 2);
    if (lane < 16 && (lane & 3) == 0) S.red[64 + warp * 4 + (lane >> 2)] = l;
    asm volatile("bar.sync 1, 256;");
    if (tid < 4) { float s = 0; for (int i = 0; i < 8; i++) s += S.red[64 + i * 4 + tid]; stg(&g_ml[cta * 8 + tid], tagw(mx, tag)); stg(&g_ml[cta * 8 + 4 + tid], tagw(s, tag)); }
    float o[16][4];
#pragma unroll
    for (int n = 0; n < 16; n++) { o[n][0] = o[n][1] = o[n][2] = o[n][3] = 0; }
#pragma unroll
    for (int t = 0; t < 8; t++) {
        WAITF();
        int key = warp * 16 + (mi & 1) * 8 + (lane & 7);
        uint32_t base = sl0 + (f % NSLOT) * SLOTB + key * 128;
#pragma unroll
        for (int n = 0; n < 8; n++) {
            uint32_t b0, b1_, b2_, b3; int ch = (n & 3) * 2 + (mi >> 1);
            asm volatile("ldmatrix.sync.aligned.m8n8.x4.trans.shared.b16 {%0,%1,%2,%3}, [%4];" : "=r"(b0), "=r"(b1_), "=r"(b2_), "=r"(b3) : "r"(base + (n >> 2) * 16384 + ((ch ^ (key & 7)) << 4)));
            mma(o[2 * n], pa[t][0], pa[t][1], b0, b1_); mma(o[2 * n + 1], pa[t][0], pa[t][1], b2_, b3);
        }
        RELF();
    }
    if (lane < 16) {
#pragma unroll
        for (int n = 0; n < 16; n++) { float* d = &S.obuf[warp * 512 + (lane >> 2) * 128 + n * 8 + (lane & 3) * 2]; d[0] = o[n][0]; d[1] = o[n][1]; }
    }
    if (tid < 4) {
        unsigned mv[8], lv[8];
        for (int i = 0; i < 8; i++) {
            for (int it = 0; it < (1 << 22); it++) { mv[i] = ldg1(&g_ml[(grp * 8 + i) * 8 + tid]); lv[i] = ldg1(&g_ml[(grp * 8 + i) * 8 + 4 + tid]); if ((mv[i] & 3) == tag && (lv[i] & 3) == tag) break; }
        }
        float M = -1e30f; for (int i = 0; i < 8; i++) M = fmaxf(M, __uint_as_float(mv[i]));
        float L = 0; for (int i = 0; i < 8; i++) L += __uint_as_float(lv[i]) * exp2f(__uint_as_float(mv[i]) - M);
        S.stat[tid] = exp2f(__uint_as_float(mv[cta & 7]) - M) / L;
    }
    asm volatile("bar.sync 1, 256;");
    for (int e = tid; e < 512; e += 256) {
        float s = 0; for (int i = 0; i < 8; i++) s += S.obuf[i * 512 + e];
        st_cl(s32(&S.recv[r * 128 + (e & 127)]), e >> 7, s * S.stat[e >> 7]);
    }
    cl_sync();
    if (tid < 128) S.xn[tid] = S.recv[tid] + S.recv[128 + tid] + S.recv[256 + tid] + S.recv[384 + tid];
    asm volatile("bar.sync 1, 256;");
    {
        float a0 = 0, a1 = 0;
        for (int qd = 0; qd < 4; qd++) {
            WAITF();
            const uint32_t* w = (const uint32_t*)(S.slots + (f % NSLOT) * SLOTB);
#pragma unroll 8
            for (int i = 0; i < 32; i++) { float2 wv = bf2(w[i * 256 + tid]); float ov = S.xn[qd * 32 + i]; a0 += ov * wv.x; a1 += ov * wv.y; }
            RELF();
        }
        cl_sync();
        st_cl(s32(&S.recv[r * 128 + ((2 * tid) & 127)]), tid >> 6, a0); st_cl(s32(&S.recv[r * 128 + ((2 * tid + 1) & 127)]), tid >> 6, a1);
    }
    cl_sync();
    if (tid < 128) stg(&g_x1[(cta >> 2) * 512 + r * 128 + tid], tagw(S.recv[tid] + S.recv[128 + tid] + S.recv[256 + tid] + S.recv[384 + tid], tag));
    for (int bb = 0; bb < 2; bb++) for (int e = tid; e < 512; e += 256) {
        unsigned v[16];
        for (int it = 0; it < (1 << 22); it++) {
            bool ok = true;
#pragma unroll
            for (int i = 0; i < 16; i++) { v[i] = ldg1(&g_x1[(bb * 16 + i) * 512 + e]); ok &= (v[i] & 3) == tag; }
            if (ok) break;
        }
        float s = 0; for (int i = 0; i < 16; i++) s += __uint_as_float(v[i]);
        S.h[bb * 512 + e] = bfr(__bfloat162float(x[bb * 512 + e]) + bfr(s));
    }
    asm volatile("bar.sync 1, 256;");
    if (cta < NFF) {
        layernorm(S.h, S.xn, S.red, tid); layernorm(S.h + 512, S.xn + 512, S.red + 16, tid);
        WAITF();
        const uint32_t* w = (const uint32_t*)(S.slots + (f % NSLOT) * SLOTB);
        float a[4] = {0, 0, 0, 0};
#pragma unroll
        for (int i = 0; i < 16; i++) { int row = (tid >> 3) * 16 + i; float2 wv = bf2(w[row * 8 + (tid & 7)]); float x0 = S.xn[row], x1 = S.xn[512 + row]; a[0] += x0 * wv.x; a[1] += x0 * wv.y; a[2] += x1 * wv.x; a[3] += x1 * wv.y; }
        for (int i = 0; i < 4; i++) { a[i] += __shfl_xor_sync(~0u, a[i], 8); a[i] += __shfl_xor_sync(~0u, a[i], 16); }
        if (lane < 8) for (int i = 0; i < 4; i++) S.obuf[warp * 32 + (i >> 1) * 16 + lane * 2 + (i & 1)] = a[i];
        asm volatile("bar.sync 1, 256;");
        if (tid < 32) {
            float u = 0; for (int i = 0; i < 8; i++) u += S.obuf[i * 32 + tid];
            u = bfr(bfr(u) + __bfloat162float(b1[cta * 16 + (tid & 15)]));
            S.g[tid] = bfr(0.5f * u * (1.f + tanhf(0.7978845608028654f * (u + 0.044715f * u * u * u))));
        }
        asm volatile("bar.sync 1, 256;");
        const uint32_t* w2s = w + 4096;
        float y[4] = {0, 0, 0, 0};
#pragma unroll
        for (int i = 0; i < 16; i++) { float2 wv = bf2(w2s[i * 256 + tid]); float g0 = S.g[i], g1 = S.g[16 + i]; y[0] += g0 * wv.x; y[1] += g0 * wv.y; y[2] += g1 * wv.x; y[3] += g1 * wv.y; }
        for (int i = 0; i < 4; i++) stg(&g_x2[((i >> 1) * 512 + 2 * tid + (i & 1)) * NFF + cta], tagw(y[i], tag));
    }
    {
        int e = cta * 8 + warp; uint4 v = make_uint4(0, 0, 0, 0);
        for (int it = 0; it < (1 << 22); it++) {
            bool ok = true;
            if (lane < 28) { v = ldg4(&g_x2[e * NFF + lane * 4]); ok = (v.x & 3) == tag && (v.y & 3) == tag && (v.z & 3) == tag && (v.w & 3) == tag; }
            if (__all_sync(~0u, ok)) break;
        }
        float s = __uint_as_float(v.x) + __uint_as_float(v.y) + __uint_as_float(v.z) + __uint_as_float(v.w);
        for (int o2 = 16; o2; o2 >>= 1) s += __shfl_xor_sync(~0u, s, o2);
        if (lane == 0) out[e] = __float2bfloat16(S.h[e] + bfr(bfr(s) + __bfloat162float(b2[e & 511])));
    }
    if (cta == 0) { asm volatile("bar.sync 1, 256;"); if (tid == 0) g_epoch = g_epoch + 1; }
}

typedef CUresult (*EncFn)(CUtensorMap*, CUtensorMapDataType, cuuint32_t, void*, const cuuint64_t*, const cuuint64_t*, const cuuint32_t*, const cuuint32_t*, CUtensorMapInterleave, CUtensorMapSwizzle, CUtensorMapL2promotion, CUtensorMapFloatOOBfill);
static void mk(EncFn fn, CUtensorMap* m, void* p, uint64_t rows, uint64_t cols, uint32_t bc, uint32_t br, CUtensorMapSwizzle sw) {
    cuuint64_t d[2] = {cols, rows}, s[1] = {cols * 2}; cuuint32_t bx[2] = {bc, br}, es[2] = {1, 1};
    fn(m, CU_TENSOR_MAP_DATA_TYPE_BFLOAT16, 2, p, d, s, bx, es, CU_TENSOR_MAP_INTERLEAVE_NONE, sw, CU_TENSOR_MAP_L2_PROMOTION_L2_256B, CU_TENSOR_MAP_FLOAT_OOB_FILL_NONE);
}
extern "C" void kernel_launch(void* const* d_in, const int* in_sizes, int n_in, void* d_out, int out_size) {
    void* fp = nullptr; cudaDriverEntryPointQueryResult qr;
    cudaGetDriverEntryPoint("cuTensorMapEncodeTiled", &fp, cudaEnableDefault, &qr);
    EncFn fn = (EncFn)fp;
    CUtensorMap mK, mV, mQ, m1;
    mk(fn, &mK, d_in[1], 131072, 128, 64, 128, CU_TENSOR_MAP_SWIZZLE_128B);
    mk(fn, &mV, d_in[2], 131072, 128, 64, 128, CU_TENSOR_MAP_SWIZZLE_128B);
    mk(fn, &mQ, d_in[3], 512, 4096, 64, 256, CU_TENSOR_MAP_SWIZZLE_NONE);
    mk(fn, &m1, d_in[6], 512, 1792, 16, 256, CU_TENSOR_MAP_SWIZZLE_NONE);
    int smem = sizeof(Sm) + 1024;
    cudaFuncSetAttribute(fused, cudaFuncAttributeMaxDynamicSharedMemorySize, smem);
    cudaLaunchConfig_t c = {}; c.gridDim = dim3(128); c.blockDim = dim3(288); c.dynamicSmemBytes = smem; c.stream = cudaStreamPerThread;
    cudaLaunchAttribute a[1]; a[0].id = cudaLaunchAttributeClusterDimension; a[0].val.clusterDim.x = 4; a[0].val.clusterDim.y = 1; a[0].val.clusterDim.z = 1;
    c.attrs = a; c.numAttrs = 1;
    cudaLaunchKernelEx(&c, fused, mK, mV, mQ, m1, (const __nv_bfloat16*)d_in[0], (const __nv_bfloat16*)d_in[4], (const __nv_bfloat16*)d_in[7],
                       (const __nv_bfloat16*)d_in[8], (const __nv_bfloat16*)d_in[9], (__nv_bfloat16*)d_out);
}
```

```cpp
#include <cuda_runtime.h>
#include <cuda_bf16.h>
#include <cuda.h>
#include <stdint.h>

#define NSLOT 6
#define SLOTB 32768
#define NFILL 21
#define NFF 112
#define QEARLY 4
__device__ unsigned g_epoch = 1;
__device__ unsigned g_ml[128 * 8];
__device__ unsigned g_q[16 * 512];
__device__ unsigned g_o[128 * 512];
__device__ unsigned g_y[128 * 512];
__device__ unsigned g_x1[16 * 512];
__device__ unsigned g_x2[1024 * NFF];

__device__ __forceinline__ uint32_t s32(const void* p) { return (uint32_t)__cvta_generic_to_shared(p); }
__device__ __forceinline__ void mb_init(uint32_t b, int c) { asm volatile("mbarrier.init.shared::cta.b64 [%0], %1;" ::"r"(b), "r"(c)); }
__device__ __forceinline__ void mb_wait(uint32_t b, uint32_t ph) {
    uint32_t ok = 0;
    for (int it = 0; it < (1 << 20) && !ok; it++)
        asm volatile("{.reg .pred p; mbarrier.try_wait.parity.shared::cta.b64 p, [%1], %2; selp.u32 %0,1,0,p;}" : "=r"(ok) : "r"(b), "r"(ph) : "memory");
}
__device__ __forceinline__ void mb_arrive(uint32_t b) { asm volatile("mbarrier.arrive.shared::cta.b64 _, [%0];" ::"r"(b) : "memory"); }
__device__ __forceinline__ void mb_expect(uint32_t b, uint32_t n) { asm volatile("mbarrier.arrive.expect_tx.shared::cta.b64 _, [%0], %1;" ::"r"(b), "r"(n) : "memory"); }
__device__ __forceinline__ void tma2d(uint32_t dst, const CUtensorMap* m, int c0, int c1, uint32_t b) {
    asm volatile("cp.async.bulk.tensor.2d.shared::cluster.global.mbarrier::complete_tx::bytes [%0], [%1, {%3, %4}], [%2];" ::"r"(dst), "l"(m), "r"(b), "r"(c0), "r"(c1) : "memory");
}
__device__ __forceinline__ void bulk1d(uint32_t dst, const void* src, uint32_t n, uint32_t b) {
    asm volatile("cp.async.bulk.shared::cluster.global.mbarrier::complete_tx::bytes [%0], [%1], %2, [%3];" ::"r"(dst), "l"(src), "r"(n), "r"(b) : "memory");
}
__device__ __forceinline__ void cl_sync() {
    asm volatile("barrier.cluster.arrive.release.aligned;\nbarrier.cluster.wait.acquire.aligned;" ::: "memory");
}
__device__ __forceinline__ void st_cl(uint32_t laddr, int rank, float v) {
    uint32_t ra;
    asm volatile("mapa.shared::cluster.u32 %0, %1, %2;" : "=r"(ra) : "r"(laddr), "r"(rank));
    asm volatile("st.shared::cluster.f32 [%0], %1;" ::"r"(ra), "f"(v) : "memory");
}
__device__ __forceinline__ void mma(float* c, uint32_t a0, uint32_t a2, uint32_t b0, uint32_t b1) {
    asm volatile("mma.sync.aligned.m16n8k16.row.col.f32.bf16.bf16.f32 {%0,%1,%2,%3}, {%4,%5,%6,%5}, {%7,%8}, {%0,%1,%2,%3};"
                 : "+f"(c[0]), "+f"(c[1]), "+f"(c[2]), "+f"(c[3]) : "r"(a0), "r"(0u), "r"(a2), "r"(b0), "r"(b1));
}
__device__ __forceinline__ unsigned tagw(float v, unsigned t) { return (__float_as_uint(v) & ~3u) | t; }
__device__ __forceinline__ void stg(unsigned* p, unsigned v) { asm volatile("st.relaxed.gpu.global.u32 [%0], %1;" ::"l"(p), "r"(v) : "memory"); }
__device__ __forceinline__ unsigned ldg1(const unsigned* p) { unsigned v; asm volatile("ld.relaxed.gpu.global.u32 %0, [%1];" : "=r"(v) : "l"(p) : "memory"); return v; }
__device__ __forceinline__ uint4 ldg4(const unsigned* p) { uint4 v; asm volatile("ld.relaxed.gpu.global.v4.u32 {%0,%1,%2,%3}, [%4];" : "=r"(v.x), "=r"(v.y), "=r"(v.z), "=r"(v.w) : "l"(p) : "memory"); return v; }
__device__ __forceinline__ float bfr(float v) { return __bfloat162float(__float2bfloat16(v)); }
__device__ __forceinline__ float2 bf2(uint32_t u) { return make_float2(__uint_as_float(u << 16), __uint_as_float(u & 0xffff0000u)); }
__device__ __forceinline__ uint32_t pk(float a, float b) { __nv_bfloat162 h = __floats2bfloat162_rn(a, b); return *(uint32_t*)&h; }

#define TS(i)
struct Sm {
    unsigned char slots[NSLOT * SLOTB];
    float obuf[8 * 512];
    float xn[1024];
    float h[1024];
    float recv[4 * 128];
    float red[8 * 32];
    __nv_bfloat16 q[512];
    float stat[64];
    float g[32];
    unsigned long long full[NSLOT], empty[NSLOT], qbar;
};

__device__ void layernorm(const float* src, float* dst, float* red, int tid) {
    float a = src[tid], b = src[tid + 256];
    float s = a + b;
    for (int o = 16; o; o >>= 1) s += __shfl_xor_sync(~0u, s, o);
    if ((tid & 31) == 0) red[tid >> 5] = s;
    asm volatile("bar.sync 1, 256;");
    s = 0; for (int i = 0; i < 8; i++) s += red[i];
    float m = s * (1.f / 512);
    float v = (a - m) * (a - m) + (b - m) * (b - m);
    for (int o = 16; o; o >>= 1) v += __shfl_xor_sync(~0u, v, o);
    if ((tid & 31) == 0) red[8 + (tid >> 5)] = v;
    asm volatile("bar.sync 1, 256;");
    v = 0; for (int i = 0; i < 8; i++) v += red[8 + i];
    float den = bfr(sqrtf(bfr(bfr(v * (1.f / 512)) + 1e-5f)));
    float mr = bfr(m);
    dst[tid] = bfr(bfr(a - mr) / den); dst[tid + 256] = bfr(bfr(b - mr) / den);
    asm volatile("bar.sync 1, 256;");
}

__global__ void __launch_bounds__(288, 1) fused(const __grid_constant__ CUtensorMap mk, const __grid_constant__ CUtensorMap mv,
    const __grid_constant__ CUtensorMap mq, const __grid_constant__ CUtensorMap m1,
    const __nv_bfloat16* __restrict__ x, const __nv_bfloat16* __restrict__ wo, const __nv_bfloat16* __restrict__ b1,
    const __nv_bfloat16* __restrict__ w2, const __nv_bfloat16* __restrict__ b2, __nv_bfloat16* __restrict__ out) {
    extern __shared__ unsigned char raw[];
    Sm& S = *(Sm*)(((uintptr_t)raw + 1023) & ~(uintptr_t)1023);
    const int tid = threadIdx.x, warp = tid >> 5, lane = tid & 31;
    const int cta = blockIdx.x, r = cta & 7, grp = cta >> 3, b = grp >> 3, hkv = grp & 7;
    const uint32_t sl0 = s32(S.slots), fb = s32(S.full), eb = s32(S.empty);
    if (tid == 0) {
        for (int i = 0; i < NSLOT; i++) { mb_init(fb + 8 * i, 1); mb_init(eb + 8 * i, 8); }
        mb_init(s32(&S.qbar), 1);
        asm volatile("fence.mbarrier_init.release.cluster;" ::: "memory");
    }
    __syncthreads();
    if (warp == 8) {
        for (int f = 0; f < NFILL; f++) {
            if (lane == 0 && !(f == 20 && cta >= NFF)) {
                int s = f % NSLOT; uint32_t d = sl0 + s * SLOTB, bar = fb + 8 * s;
                if (f == 2) { mb_wait(fb, 0); mb_wait(fb + 8, 0); }
                if (f == QEARLY) mb_wait(s32(&S.qbar), 0);
                mb_wait(eb + 8 * s, ((f / NSLOT) & 1) ^ 1);
                mb_expect(bar, SLOTB);
                if (f < 2) tma2d(d, &mq, hkv * 512 + r * 64, f * 256, bar);
                else if (f < 18) {
                    const CUtensorMap* m = f < 10 ? &mk : &mv; int row = cta * 1024 + ((f - 2) & 7) * 128;
                    tma2d(d, m, 0, row, bar); tma2d(d + 16384, m, 64, row, bar);
                } else if (f < 20) bulk1d(d, wo + (size_t)(hkv * 512 + r * 64 + (f - 18) * 32) * 512, SLOTB, bar);
                else { tma2d(d, &m1, cta * 16, 0, bar); tma2d(d + 8192, &m1, cta * 16, 256, bar); bulk1d(d + 16384, w2 + (size_t)cta * 16 * 512, 16384, bar); }
            }
            __syncwarp();
        }
        return;
    }
    TS(0);
    const unsigned tag = ldg1(&g_epoch) & 3;
    int f = 0;
    const float b1v = __bfloat162float(b1[min(cta, NFF - 1) * 16 + (tid & 15)]), b2v = __bfloat162float(b2[(cta * 8 + warp) & 511]);
    float xv4[4];
#pragma unroll
    for (int j = 0; j < 4; j++) xv4[j] = __bfloat162float(x[j * 256 + tid]);
#define WAITF() mb_wait(fb + 8 * (f % NSLOT), (f / NSLOT) & 1)
#define RELF() do { __syncwarp(); if (lane == 0) mb_arrive(eb + 8 * (f % NSLOT)); f++; } while (0)
    S.h[tid] = __bfloat162float(x[b * 512 + tid]); S.h[tid + 256] = __bfloat162float(x[b * 512 + 256 + tid]);
    asm volatile("bar.sync 1, 256;");
    layernorm(S.h, S.xn, S.red, tid);
    TS(9);
    {
        float a0 = 0, a1 = 0;
        for (int rh = 0; rh < 2; rh++) {
            WAITF();
            const uint32_t* w = (const uint32_t*)(S.slots + (f % NSLOT) * SLOTB);
#pragma unroll 8
            for (int i = 0; i < 32; i++) { int row = warp * 32 + i; float2 wv = bf2(w[row * 32 + lane]); float xv = S.xn[rh * 256 + row]; a0 += xv * wv.x; a1 += xv * wv.y; }
            RELF();
        }
        TS(10);
        S.obuf[warp * 64 + lane * 2] = a0; S.obuf[warp * 64 + lane * 2 + 1] = a1;
        asm volatile("bar.sync 1, 256;");
        if (tid < 64) { float sm = 0; for (int i = 0; i < 8; i++) sm += S.obuf[i * 64 + tid]; stg(&g_q[grp * 512 + r * 64 + tid], tagw(sm, tag)); }
        for (int e = tid; e < 512; e += 256) {
            unsigned v = 0;
            for (int it = 0; it < (1 << 18); it++) { v = ldg1(&g_q[grp * 512 + e]); if ((v & 3) == tag) break; }
            S.q[e] = __float2bfloat16(__uint_as_float(v));
        }
        asm volatile("bar.sync 1, 256;");
    }
    if (tid == 0) mb_arrive(s32(&S.qbar));
    TS(1);
    uint32_t qa[8][2];
    {
        int row = lane >> 2; const uint32_t* qw = (const uint32_t*)S.q;
#pragma unroll
        for (int k = 0; k < 8; k++) { qa[k][0] = row < 4 ? qw[row * 64 + k * 8 + (lane & 3)] : 0; qa[k][1] = row < 4 ? qw[row * 64 + k * 8 + 4 + (lane & 3)] : 0; }
    }
    float sc[8][4];
    const int mi = lane >> 3;
#pragma unroll
    for (int t = 0; t < 8; t++) {
        WAITF();
        float c0[4] = {0, 0, 0, 0}, c1[4] = {0, 0, 0, 0};
        int key = warp * 16 + (mi >> 1) * 8 + (lane & 7);
        uint32_t base = sl0 + (f % NSLOT) * SLOTB + key * 128;
#pragma unroll
        for (int k = 0; k < 8; k++) {
            uint32_t b0, b1_, b2_, b3; int ch = (k & 3) * 2 + (mi & 1);
            asm volatile("ldmatrix.sync.aligned.m8n8.x4.shared.b16 {%0,%1,%2,%3}, [%4];" : "=r"(b0), "=r"(b1_), "=r"(b2_), "=r"(b3) : "r"(base + (k >> 2) * 16384 + ((ch ^ (key & 7)) << 4)));
            mma(c0, qa[k][0], qa[k][1], b0, b1_); mma(c1, qa[k][0], qa[k][1], b2_, b3);
        }
        RELF();
        const float sq = 0.08838834764831845f; sc[t][0] = bfr(bfr(c0[0]) * sq); sc[t][1] = bfr(bfr(c0[1]) * sq); sc[t][2] = bfr(bfr(c1[0]) * sq); sc[t][3] = bfr(bfr(c1[1]) * sq);
    }
    TS(2);
    const float kS = 1.4426950408889634f;
    float mx = -1e30f;
#pragma unroll
    for (int t = 0; t < 8; t++) for (int i = 0; i < 4; i++) mx = fmaxf(mx, sc[t][i] * kS);
    mx = fmaxf(mx, __shfl_xor_sync(~0u, mx, 1)); mx = fmaxf(mx, __shfl_xor_sync(~0u, mx, 2));
    if (lane < 16 && (lane & 3) == 0) S.red[warp * 4 + (lane >> 2)] = mx;
    asm volatile("bar.sync 1, 256;");
    { int row = (lane >> 2) & 3; mx = S.red[row]; for (int i = 1; i < 8; i++) mx = fmaxf(mx, S.red[i * 4 + row]); }
    uint32_t pa[8][2]; float l = 0;
#pragma unroll
    for (int t = 0; t < 8; t++) {
        float p[4]; for (int i = 0; i < 4; i++) { p[i] = bfr(exp2f(sc[t][i] * kS - mx)); l += p[i]; }
        pa[t][0] = pk(p[0], p[1]); pa[t][1] = pk(p[2], p[3]);
    }
    l += __shfl_xor_sync(~0u, l, 1); l += __shfl_xor_sync(~0u, l, 2);
    if (lane < 16 && (lane & 3) == 0) S.red[64 + warp * 4 + (lane >> 2)] = l;
    asm volatile("bar.sync 1, 256;");
    if (tid < 4) { float s = 0, m2 = -1e30f; for (int i = 0; i < 8; i++) { s += S.red[64 + i * 4 + tid]; m2 = fmaxf(m2, S.red[i * 4 + tid]); } stg(&g_ml[cta * 8 + tid], tagw(m2, tag)); stg(&g_ml[cta * 8 + 4 + tid], tagw(s, tag)); }
    float o[16][4];
#pragma unroll
    for (int n = 0; n < 16; n++) { o[n][0] = o[n][1] = o[n][2] = o[n][3] = 0; }
#pragma unroll
    for (int t = 0; t < 8; t++) {
        WAITF();
        int key = warp * 16 + (mi & 1) * 8 + (lane & 7);
        uint32_t base = sl0 + (f % NSLOT) * SLOTB + key * 128;
#pragma unroll
        for (int n = 0; n < 8; n++) {
            uint32_t b0, b1_, b2_, b3; int ch = (n & 3) * 2 + (mi >> 1);
            asm volatile("ldmatrix.sync.aligned.m8n8.x4.trans.shared.b16 {%0,%1,%2,%3}, [%4];" : "=r"(b0), "=r"(b1_), "=r"(b2_), "=r"(b3) : "r"(base + (n >> 2) * 16384 + ((ch ^ (key & 7)) << 4)));
            mma(o[2 * n], pa[t][0], pa[t][1], b0, b1_); mma(o[2 * n + 1], pa[t][0], pa[t][1], b2_, b3);
        }
        RELF();
    }
    TS(3);
    if (lane < 16) {
#pragma unroll
        for (int n = 0; n < 16; n++) { float* d = &S.obuf[warp * 512 + (lane >> 2) * 128 + n * 8 + (lane & 3) * 2]; d[0] = o[n][0]; d[1] = o[n][1]; }
    }
    if (tid < 4) {
        unsigned mv[8], lv[8];
        for (int i = 0; i < 8; i++) {
            for (int it = 0; it < (1 << 18); it++) { mv[i] = ldg1(&g_ml[(grp * 8 + i) * 8 + tid]); lv[i] = ldg1(&g_ml[(grp * 8 + i) * 8 + 4 + tid]); if ((mv[i] & 3) == tag && (lv[i] & 3) == tag) break; }
        }
        float M = -1e30f; for (int i = 0; i < 8; i++) M = fmaxf(M, __uint_as_float(mv[i]));
        float L = 0; for (int i = 0; i < 8; i++) L += __uint_as_float(lv[i]) * exp2f(__uint_as_float(mv[i]) - M);
        S.stat[tid] = exp2f(__uint_as_float(mv[cta & 7]) - M) / L;
    }
    asm volatile("bar.sync 1, 256;");
    for (int e = tid; e < 512; e += 256) {
        float sm = 0; for (int i = 0; i < 8; i++) sm += S.obuf[i * 512 + e];
        stg(&g_o[cta * 512 + e], tagw(sm * S.stat[e >> 7], tag));
    }
    if (tid < 64) {
        unsigned v[8];
        for (int it = 0; it < (1 << 18); it++) {
            bool ok = true;
#pragma unroll
            for (int i = 0; i < 8; i++) { v[i] = ldg1(&g_o[(grp * 8 + i) * 512 + r * 64 + tid]); ok &= (v[i] & 3) == tag; }
            if (ok) break;
        }
        float sm = 0; for (int i = 0; i < 8; i++) sm += __uint_as_float(v[i]);
        S.xn[tid] = sm;
    }
    asm volatile("bar.sync 1, 256;");
    TS(4);
    {
        float a0 = 0, a1 = 0;
        for (int qd = 0; qd < 2; qd++) {
            WAITF();
            const uint32_t* w = (const uint32_t*)(S.slots + (f % NSLOT) * SLOTB);
#pragma unroll 8
            for (int i = 0; i < 32; i++) { float2 wv = bf2(w[i * 256 + tid]); float ov = S.xn[qd * 32 + i]; a0 += ov * wv.x; a1 += ov * wv.y; }
            RELF();
        }
        stg(&g_y[cta * 512 + 2 * tid], tagw(a0, tag)); stg(&g_y[cta * 512 + 2 * tid + 1], tagw(a1, tag));
    }
    if (tid < 64) {
        unsigned v[8];
        for (int it = 0; it < (1 << 18); it++) {
            bool ok = true;
#pragma unroll
            for (int i = 0; i < 8; i++) { v[i] = ldg1(&g_y[(grp * 8 + i) * 512 + r * 64 + tid]); ok &= (v[i] & 3) == tag; }
            if (ok) break;
        }
        float sm = 0; for (int i = 0; i < 8; i++) sm += __uint_as_float(v[i]);
        stg(&g_x1[grp * 512 + r * 64 + tid], tagw(sm, tag));
    }
    TS(5);
    {
        unsigned v[4][8];
        for (int it = 0; it < (1 << 18); it++) {
            bool ok = true;
#pragma unroll
            for (int j = 0; j < 4; j++)
#pragma unroll
                for (int i = 0; i < 8; i++) { v[j][i] = ldg1(&g_x1[((j >> 1) * 8 + i) * 512 + (j & 1) * 256 + tid]); ok &= (v[j][i] & 3) == tag; }
            if (ok) break;
        }
#pragma unroll
        for (int j = 0; j < 4; j++) {
            float sm = 0; for (int i = 0; i < 8; i++) sm += __uint_as_float(v[j][i]);
            S.h[j * 256 + tid] = bfr(xv4[j] + bfr(sm));
        }
    }
    asm volatile("bar.sync 1, 256;");
    TS(6);
    if (cta < NFF) {
        {
            const int hb = warp >> 2, t2 = tid & 127; const float* src = S.h + hb * 512;
            float e0 = src[t2], e1 = src[t2 + 128], e2 = src[t2 + 256], e3 = src[t2 + 384];
            float sm = e0 + e1 + e2 + e3;
            for (int o2 = 16; o2; o2 >>= 1) sm += __shfl_xor_sync(~0u, sm, o2);
            if (lane == 0) S.red[warp] = sm;
            asm volatile("bar.sync 1, 256;");
            float m = (S.red[hb * 4] + S.red[hb * 4 + 1] + S.red[hb * 4 + 2] + S.red[hb * 4 + 3]) * (1.f / 512);
            float vv = (e0 - m) * (e0 - m) + (e1 - m) * (e1 - m) + (e2 - m) * (e2 - m) + (e3 - m) * (e3 - m);
            for (int o2 = 16; o2; o2 >>= 1) vv += __shfl_xor_sync(~0u, vv, o2);
            if (lane == 0) S.red[8 + warp] = vv;
            asm volatile("bar.sync 1, 256;");
            vv = S.red[8 + hb * 4] + S.red[8 + hb * 4 + 1] + S.red[8 + hb * 4 + 2] + S.red[8 + hb * 4 + 3];
            float den = bfr(sqrtf(bfr(bfr(vv * (1.f / 512)) + 1e-5f))), mr = bfr(m);
            float* dst = S.xn + hb * 512;
            dst[t2] = bfr(bfr(e0 - mr) / den); dst[t2 + 128] = bfr(bfr(e1 - mr) / den); dst[t2 + 256] = bfr(bfr(e2 - mr) / den); dst[t2 + 384] = bfr(bfr(e3 - mr) / den);
            asm volatile("bar.sync 1, 256;");
        }
        WAITF();
        const uint32_t* w = (const uint32_t*)(S.slots + (f % NSLOT) * SLOTB);
        float a[4] = {0, 0, 0, 0};
#pragma unroll
        for (int i = 0; i < 16; i++) { int row = (tid >> 3) * 16 + i; float2 wv = bf2(w[row * 8 + (tid & 7)]); float x0 = S.xn[row], x1 = S.xn[512 + row]; a[0] += x0 * wv.x; a[1] += x0 * wv.y; a[2] += x1 * wv.x; a[3] += x1 * wv.y; }
        for (int i = 0; i < 4; i++) { a[i] += __shfl_xor_sync(~0u, a[i], 8); a[i] += __shfl_xor_sync(~0u, a[i], 16); }
        if (lane < 8) for (int i = 0; i < 4; i++) S.obuf[warp * 32 + (i >> 1) * 16 + lane * 2 + (i & 1)] = a[i];
        asm volatile("bar.sync 1, 256;");
        if (tid < 32) {
            float u = 0; for (int i = 0; i < 8; i++) u += S.obuf[i * 32 + tid];
            u = bfr(bfr(u) + b1v);
            S.g[tid] = bfr(0.5f * u * (1.f + tanhf(0.7978845608028654f * (u + 0.044715f * u * u * u))));
        }
        asm volatile("bar.sync 1, 256;");
        const uint32_t* w2s = w + 4096;
        float y[4] = {0, 0, 0, 0};
#pragma unroll
        for (int i = 0; i < 16; i++) { float2 wv = bf2(w2s[i * 256 + tid]); float g0 = S.g[i], g1 = S.g[16 + i]; y[0] += g0 * wv.x; y[1] += g0 * wv.y; y[2] += g1 * wv.x; y[3] += g1 * wv.y; }
        for (int i = 0; i < 4; i++) stg(&g_x2[cta * 1024 + (i >> 1) * 512 + 2 * tid + (i & 1)], tagw(y[i], tag));
    }
    TS(7);
    {
        if (tid < 2 * NFF) {
            uint4 v;
            for (int it = 0; it < (1 << 18); it++) {
                v = ldg4(&g_x2[(tid >> 1) * 1024 + cta * 8 + (tid & 1) * 4]);
                if ((v.x & 3) == tag && (v.y & 3) == tag && (v.z & 3) == tag && (v.w & 3) == tag) break;
            }
            *(uint4*)&S.obuf[tid * 4] = v;
        }
        asm volatile("bar.sync 1, 256;");
        float sm = 0;
        for (int j = lane; j < NFF; j += 32) sm += S.obuf[j * 8 + warp];
        for (int o2 = 16; o2; o2 >>= 1) sm += __shfl_xor_sync(~0u, sm, o2);
        int e = cta * 8 + warp;
        if (lane == 0) out[e] = __float2bfloat16(S.h[e] + bfr(bfr(sm) + b2v));
    }
    TS(8);
    if (cta == 0) { asm volatile("bar.sync 1, 256;"); if (tid == 0) g_epoch = g_epoch + 1; }
}

typedef CUresult (*EncFn)(CUtensorMap*, CUtensorMapDataType, cuuint32_t, void*, const cuuint64_t*, const cuuint64_t*, const cuuint32_t*, const cuuint32_t*, CUtensorMapInterleave, CUtensorMapSwizzle, CUtensorMapL2promotion, CUtensorMapFloatOOBfill);
static void mk(EncFn fn, CUtensorMap* m, void* p, uint64_t rows, uint64_t cols, uint32_t bc, uint32_t br, CUtensorMapSwizzle sw) {
    cuuint64_t d[2] = {cols, rows}, s[1] = {cols * 2}; cuuint32_t bx[2] = {bc, br}, es[2] = {1, 1};
    fn(m, CU_TENSOR_MAP_DATA_TYPE_BFLOAT16, 2, p, d, s, bx, es, CU_TENSOR_MAP_INTERLEAVE_NONE, sw, CU_TENSOR_MAP_L2_PROMOTION_L2_256B, CU_TENSOR_MAP_FLOAT_OOB_FILL_NONE);
}
extern "C" void kernel_launch(void* const* d_in, const int* in_sizes, int n_in, void* d_out, int out_size) {
    void* fp = nullptr; cudaDriverEntryPointQueryResult qr;
    cudaGetDriverEntryPoint("cuTensorMapEncodeTiled", &fp, cudaEnableDefault, &qr);
    EncFn fn = (EncFn)fp;
    CUtensorMap mK, mV, mQ, m1;
    mk(fn, &mK, d_in[1], 131072, 128, 64, 128, CU_TENSOR_MAP_SWIZZLE_128B);
    mk(fn, &mV, d_in[2], 131072, 128, 64, 128, CU_TENSOR_MAP_SWIZZLE_128B);
    mk(fn, &mQ, d_in[3], 512, 4096, 64, 256, CU_TENSOR_MAP_SWIZZLE_NONE);
    mk(fn, &m1, d_in[6], 512, 1792, 16, 256, CU_TENSOR_MAP_SWIZZLE_NONE);
    int smem = sizeof(Sm) + 1024;
    cudaFuncSetAttribute(fused, cudaFuncAttributeMaxDynamicSharedMemorySize, smem);
    cudaLaunchConfig_t c = {}; c.gridDim = dim3(128); c.blockDim = dim3(288); c.dynamicSmemBytes = smem; c.stream = cudaStreamPerThread;
    cudaLaunchAttribute a[1]; a[0].id = cudaLaunchAttributeClusterDimension; a[0].val.clusterDim.x = 1; a[0].val.clusterDim.y = 1; a[0].val.clusterDim.z = 1;
    c.attrs = a; c.numAttrs = 1;
    cudaLaunchKernelEx(&c, fused, mK, mV, mQ, m1, (const __nv_bfloat16*)d_in[0], (const __nv_bfloat16*)d_in[4], (const __nv_bfloat16*)d_in[7],
                       (const __nv_bfloat16*)d_in[8], (const __nv_bfloat16*)d_in[9], (__nv_bfloat16*)d_out);
}
```
